```python
import torch

def _softmax(x, axis=-1):
    return torch.softmax(x, dim=axis)
def _gelu(x):
    return torch.nn.functional.gelu(x, approximate="tanh")
def _silu(x):
    return torch.nn.functional.silu(x)
def _sigmoid(x):
    return torch.sigmoid(x)
def _layernorm(x, axis=-1, eps=1e-5):
    m = x.mean(dim=axis, keepdim=True)
    v = x.var(dim=axis, keepdim=True, unbiased=False)
    return (x - m) / torch.sqrt(v + eps)
def _scatter_add(tgt, idx, src, axis=0):
    return tgt.clone().index_add_(axis, idx, src)
def _segment_sum(src, seg, n):
    out = torch.zeros((n,) + src.shape[1:], dtype=src.dtype)
    return out.index_add_(0, seg, src)
def _pad(x, pw):
    flat = tuple(v for pair in reversed(pw) for v in pair)
    return torch.nn.functional.pad(x, flat)

kernel_name = 'parallel_sum__ssm_conv_h3__glu_gated_geglu__prompt'

def setup_inputs():

    _w = (lambda a: (lambda t: t.to(torch.bfloat16) if t.is_floating_point() else t)(torch.as_tensor(a)))
    def _A_setup():
        B, S, D = 1, 2048, 512
        ks = 4
        return {
            "q": _w((lambda *s: torch.randn(*s, dtype=torch.bfloat16) * 0.05)(B, S, D)),
            "k": _w((lambda *s: torch.randn(*s, dtype=torch.bfloat16) * 0.2)(B, S, D)),
            "v": _w((lambda *s: torch.randn(*s, dtype=torch.bfloat16) * 0.2)(B, S, D)),
            "shift_k": _w((lambda *s: torch.randn(*s, dtype=torch.bfloat16) * 0.2)(D, ks) * 0.5),
            "ssm_k": _w((lambda *s: torch.randn(*s, dtype=torch.bfloat16) * 0.4)(D, S) * (1.0 / S ** 0.5)),
            "ssm_D": _w((lambda *s: torch.randn(*s, dtype=torch.bfloat16) * 0.2)(D)),
        }
    _A_in = _A_setup()

    def _B_setup():
        B, S, Dm, Df = 1, 2048, 512, 1792
        return {
            "x": _w((lambda *s: torch.randn(*s, dtype=torch.bfloat16) * 0.05)(B, S, Dm)),
            "w_gate": _w((lambda *s: torch.randn(*s, dtype=torch.bfloat16) * 0.4)(Dm, Df) * (Dm ** -0.5)),
            "w_up": _w((lambda *s: torch.randn(*s, dtype=torch.bfloat16) * 0.4)(Dm, Df) * (Dm ** -0.5)),
            "w_down": _w((lambda *s: torch.randn(*s, dtype=torch.bfloat16) * 0.4)(Df, Dm) * (Df ** -0.5)),
        }
    _B_in = _B_setup()

    return {
        "A_q": _A_in["q"],
        "A_k": _A_in["k"],
        "A_v": _A_in["v"],
        "A_shift_k": _A_in["shift_k"],
        "A_ssm_k": _A_in["ssm_k"],
        "A_ssm_D": _A_in["ssm_D"],
        "B_x": _B_in["x"],
        "B_w_gate": _B_in["w_gate"],
        "B_w_up": _B_in["w_up"],
        "B_w_down": _B_in["w_down"],
    }

def reference(A_q, A_k, A_v, A_shift_k, A_ssm_k, A_ssm_D, B_x, B_w_gate, B_w_up, B_w_down):
    def _A_ref(q, k, v, shift_k, ssm_k, ssm_D):
        B, S, D = q.shape
        ks = shift_k.shape[-1]
        k_pad = _pad(k, ((0, 0), (ks - 1, 0), (0, 0)))
        k_shift = torch.zeros_like(k)
        for t in range(ks):
            k_shift = k_shift + k_pad[:, t:t + S, :] * shift_k[:, ks - 1 - t][None, None, :]
        kv = k_shift * v
        L = 2 * S
        kv_pad = _pad(kv, ((0, 0), (0, S), (0, 0)))
        kf_pad = _pad(ssm_k, ((0, 0), (0, S)))
        kv_f = (lambda x, axes=(-2,-1): torch.fft.rfft2(x.float(), dim=axes))(kv_pad[:, None, :, :], axes=(1, 2))
        kf_f = (lambda x, axes=(-2,-1): torch.fft.rfft2(x.float(), dim=axes))(kf_pad[:, None, :], axes=(1, 2))
        kf_f = (lambda x, *d: x.permute(*d))(kf_f, 1, 2, 0)
        y_f = kv_f * kf_f[None, :, :, :]
        y = (lambda x, s, axes=(-2,-1): torch.fft.irfft2(x, s=s, dim=axes).to(torch.bfloat16))(y_f, (1, L), axes=(1, 2))[:, 0, :S, :]
        y = y + kv * ssm_D[None, None, :]
        return q * y

    def _B_ref(x, w_gate, w_up, w_down):
        g = torch.einsum("bsd,df->bsf", x, w_gate)
        u = torch.einsum("bsd,df->bsf", x, w_up)
        h = _gelu(g) * u
        return torch.einsum("bsf,fd->bsd", h, w_down)

    x = A_q
    xn = _layernorm(x, axis=-1)
    return x + _A_ref(xn, A_k, A_v, A_shift_k, A_ssm_k, A_ssm_D) + _B_ref(xn, B_w_gate, B_w_up, B_w_down)
```

```cpp
#include <cuda_runtime.h>
#include <cuda_bf16.h>
#include <cuda.h>
#include <stdint.h>

#define PFSLEEP 450
#define G2PRE 7
#define G2JOIN 9
#define KLAG 4
#define EPI_CHAIN 0
#define KLEAD 6
#define G2OWN 0x5555555
#define G2MC
#define W0DELAY 0
#define W1PF 500
#define G2NP 12
#define YSTR 32
#define YSLEEP 32
#define RELAT 8
#define NSET 2
#define NPS 4
namespace {

constexpr int S_ = 2048, D_ = 512, F_ = 1792;
constexpr int NSLOT = 11, SLOT = 16384;
constexpr int OFF_STG = NSLOT * SLOT;
constexpr int OFF_X = OFF_STG + 16384;
constexpr int XSTRIDE = 8320, XA_OFF = 4160;
constexpr int OFF_Z = OFF_X + 2 * XSTRIDE;
constexpr int ZSTRIDE = 4112;
constexpr int OFF_BAR = OFF_Z + 4 * ZSTRIDE;
constexpr int B_FULL = 0, B_QB = 11, B_G2F = 15, B_YT = 22, B_YFREE = 24, B_SEMPTY = 26, B_ZFULL = 28, B_KV = 30,
              B_W1GO = 31, B_PREP = 33, B_T7 = 34, B_EMPTY = 35, B_E2 = 46, B_SFULL = 53, B_G1END = 55, B_XFULL = 57,
              B_YDONE = 58, B_LAG = 62, B_TOK = 64, NBAR = 80;
constexpr int SMEM_BYTES = OFF_BAR + NBAR * 8 + 640;
constexpr int OFF_YT = OFF_X;
constexpr int OFF_YB = 3 * 8192;
constexpr unsigned G2_WSLOT = 0x0A87542;
constexpr unsigned long long G2_HSUB = 0x0213120D0C0706ull;
constexpr int OFF_BT = (G2_WSLOT & 15) * SLOT;
constexpr unsigned G1_LASTPH = 0x40C;
constexpr int G2_JOIN = G2JOIN;
constexpr int G2_PRE = G2PRE;
constexpr int G2_NP = G2NP;
constexpr unsigned long long g2_tokens() {
  unsigned long long t = 0;
  for (int i = 0; i < G2_NP; i++) t |= (unsigned long long)((i + 1) * 16 / G2_NP - 1) << (4 * i);
  return t;
}
constexpr unsigned long long G2_TOK = g2_tokens();
constexpr int FLS = 32;
constexpr int FL_H = 0, FL_KV = 512 * FLS, FL_EP = 520 * FLS, FL_Y = 648 * FLS, FL_TOTAL = FL_Y + 128 * 64;

struct Params {
  const __nv_bfloat16 *qg, *gwg, *gwu, *k, *v, *shift, *ssm, *dvec, *gwd;
  __nv_bfloat16 *ur, *yt, *outp;
  uint2* stats;
  unsigned* flags;
  CUtensorMap q, wg, wu, h, wd, y;
};

__device__ __nv_bfloat16 g_h[S_ * F_];
__device__ __nv_bfloat16 g_ur[D_ * S_];
__device__ __nv_bfloat16 g_yt[D_ * S_];
__device__ uint2 g_stats[S_];
__device__ unsigned g_flags[FL_TOTAL];
#define TS(i)
#define TS1(i)
#define TG(i)

__device__ __forceinline__ void wg_rs128_t(float* d, const uint32_t* a, uint64_t db, int sd) {
  asm volatile("{\n.reg .pred p;\nsetp.ne.b32 p, %69, 0;\n"
    "wgmma.mma_async.sync.aligned.m64n128k16.f32.bf16.bf16 {%0,%1,%2,%3,%4,%5,%6,%7,%8,%9,%10,%11,%12,%13,%14,%15,%16,%17,%18,%19,%20,%21,%22,%23,%24,%25,%26,%27,%28,%29,%30,%31,%32,%33,%34,%35,%36,%37,%38,%39,%40,%41,%42,%43,%44,%45,%46,%47,%48,%49,%50,%51,%52,%53,%54,%55,%56,%57,%58,%59,%60,%61,%62,%63}, {%64,%65,%66,%67}, %68, p, 1, 1, 1;\n}\n"
    : "+f"(d[0]),"+f"(d[1]),"+f"(d[2]),"+f"(d[3]),"+f"(d[4]),"+f"(d[5]),"+f"(d[6]),"+f"(d[7]),"+f"(d[8]),"+f"(d[9]),"+f"(d[10]),"+f"(d[11]),"+f"(d[12]),"+f"(d[13]),"+f"(d[14]),"+f"(d[15]),"+f"(d[16]),"+f"(d[17]),"+f"(d[18]),"+f"(d[19]),"+f"(d[20]),"+f"(d[21]),"+f"(d[22]),"+f"(d[23]),"+f"(d[24]),"+f"(d[25]),"+f"(d[26]),"+f"(d[27]),"+f"(d[28]),"+f"(d[29]),"+f"(d[30]),"+f"(d[31]),"+f"(d[32]),"+f"(d[33]),"+f"(d[34]),"+f"(d[35]),"+f"(d[36]),"+f"(d[37]),"+f"(d[38]),"+f"(d[39]),"+f"(d[40]),"+f"(d[41]),"+f"(d[42]),"+f"(d[43]),"+f"(d[44]),"+f"(d[45]),"+f"(d[46]),"+f"(d[47]),"+f"(d[48]),"+f"(d[49]),"+f"(d[50]),"+f"(d[51]),"+f"(d[52]),"+f"(d[53]),"+f"(d[54]),"+f"(d[55]),"+f"(d[56]),"+f"(d[57]),"+f"(d[58]),"+f"(d[59]),"+f"(d[60]),"+f"(d[61]),"+f"(d[62]),"+f"(d[63])
    : "r"(a[0]), "r"(a[1]), "r"(a[2]), "r"(a[3]), "l"(db), "r"(sd));
}
__device__ __forceinline__ void wg_ss128_t(float* d, uint64_t da, uint64_t db, int sd) {
  asm volatile("{\n.reg .pred p;\nsetp.ne.b32 p, %66, 0;\n"
    "wgmma.mma_async.sync.aligned.m64n128k16.f32.bf16.bf16 {%0,%1,%2,%3,%4,%5,%6,%7,%8,%9,%10,%11,%12,%13,%14,%15,%16,%17,%18,%19,%20,%21,%22,%23,%24,%25,%26,%27,%28,%29,%30,%31,%32,%33,%34,%35,%36,%37,%38,%39,%40,%41,%42,%43,%44,%45,%46,%47,%48,%49,%50,%51,%52,%53,%54,%55,%56,%57,%58,%59,%60,%61,%62,%63}, %64, %65, p, 1, 1, 0, 1;\n}\n"
    : "+f"(d[0]),"+f"(d[1]),"+f"(d[2]),"+f"(d[3]),"+f"(d[4]),"+f"(d[5]),"+f"(d[6]),"+f"(d[7]),"+f"(d[8]),"+f"(d[9]),"+f"(d[10]),"+f"(d[11]),"+f"(d[12]),"+f"(d[13]),"+f"(d[14]),"+f"(d[15]),"+f"(d[16]),"+f"(d[17]),"+f"(d[18]),"+f"(d[19]),"+f"(d[20]),"+f"(d[21]),"+f"(d[22]),"+f"(d[23]),"+f"(d[24]),"+f"(d[25]),"+f"(d[26]),"+f"(d[27]),"+f"(d[28]),"+f"(d[29]),"+f"(d[30]),"+f"(d[31]),"+f"(d[32]),"+f"(d[33]),"+f"(d[34]),"+f"(d[35]),"+f"(d[36]),"+f"(d[37]),"+f"(d[38]),"+f"(d[39]),"+f"(d[40]),"+f"(d[41]),"+f"(d[42]),"+f"(d[43]),"+f"(d[44]),"+f"(d[45]),"+f"(d[46]),"+f"(d[47]),"+f"(d[48]),"+f"(d[49]),"+f"(d[50]),"+f"(d[51]),"+f"(d[52]),"+f"(d[53]),"+f"(d[54]),"+f"(d[55]),"+f"(d[56]),"+f"(d[57]),"+f"(d[58]),"+f"(d[59]),"+f"(d[60]),"+f"(d[61]),"+f"(d[62]),"+f"(d[63])
    : "l"(da), "l"(db), "r"(sd));
}
__device__ __forceinline__ void wg_rs64_n(float* d, const uint32_t* a, uint64_t db, int sd) {
  asm volatile("{\n.reg .pred p;\nsetp.ne.b32 p, %37, 0;\n"
    "wgmma.mma_async.sync.aligned.m64n64k16.f32.bf16.bf16 {%0,%1,%2,%3,%4,%5,%6,%7,%8,%9,%10,%11,%12,%13,%14,%15,%16,%17,%18,%19,%20,%21,%22,%23,%24,%25,%26,%27,%28,%29,%30,%31}, {%32,%33,%34,%35}, %36, p, 1, 1, 0;\n}\n"
    : "+f"(d[0]),"+f"(d[1]),"+f"(d[2]),"+f"(d[3]),"+f"(d[4]),"+f"(d[5]),"+f"(d[6]),"+f"(d[7]),"+f"(d[8]),"+f"(d[9]),"+f"(d[10]),"+f"(d[11]),"+f"(d[12]),"+f"(d[13]),"+f"(d[14]),"+f"(d[15]),"+f"(d[16]),"+f"(d[17]),"+f"(d[18]),"+f"(d[19]),"+f"(d[20]),"+f"(d[21]),"+f"(d[22]),"+f"(d[23]),"+f"(d[24]),"+f"(d[25]),"+f"(d[26]),"+f"(d[27]),"+f"(d[28]),"+f"(d[29]),"+f"(d[30]),"+f"(d[31])
    : "r"(a[0]), "r"(a[1]), "r"(a[2]), "r"(a[3]), "l"(db), "r"(sd));
}
__device__ __forceinline__ void conv_tail(float* d, const uint32_t* a, uint64_t db) {
  asm volatile("{\n.reg .pred p0, p1;\n.reg .u64 t;\nsetp.eq.b32 p0, 0, 0;\nsetp.eq.b32 p1, 0, 0;\n"
    "add.u64 t, %44, 0;\nwgmma.mma_async.sync.aligned.m64n48k16.f32.bf16.bf16 {%0,%1,%2,%3,%4,%5,%6,%7,%8,%9,%10,%11,%12,%13,%14,%15,%16,%17,%18,%19,%20,%21,%22,%23}, {%32,%33,%34,%35}, t, p0, 1, 1, 0;\n"
    "add.u64 t, %44, 16;\nwgmma.mma_async.sync.aligned.m64n32k16.f32.bf16.bf16 {%0,%1,%2,%3,%4,%5,%6,%7,%8,%9,%10,%11,%12,%13,%14,%15}, {%36,%37,%38,%39}, t, p1, 1, 1, 0;\n"
    "add.u64 t, %44, 32;\nwgmma.mma_async.sync.aligned.m64n16k16.f32.bf16.bf16 {%0,%1,%2,%3,%4,%5,%6,%7}, {%40,%41,%42,%43}, t, p1, 1, 1, 0;\n"
    "}\n"
    : "+f"(d[0]),"+f"(d[1]),"+f"(d[2]),"+f"(d[3]),"+f"(d[4]),"+f"(d[5]),"+f"(d[6]),"+f"(d[7]),"+f"(d[8]),"+f"(d[9]),"+f"(d[10]),"+f"(d[11]),"+f"(d[12]),"+f"(d[13]),"+f"(d[14]),"+f"(d[15]),"+f"(d[16]),"+f"(d[17]),"+f"(d[18]),"+f"(d[19]),"+f"(d[20]),"+f"(d[21]),"+f"(d[22]),"+f"(d[23]),"+f"(d[24]),"+f"(d[25]),"+f"(d[26]),"+f"(d[27]),"+f"(d[28]),"+f"(d[29]),"+f"(d[30]),"+f"(d[31])
    : "r"(a[0]),"r"(a[1]),"r"(a[2]),"r"(a[3]),"r"(a[4]),"r"(a[5]),"r"(a[6]),"r"(a[7]),"r"(a[8]),"r"(a[9]),"r"(a[10]),"r"(a[11]), "l"(db));
}

#define WG_FENCE() asm volatile("wgmma.fence.sync.aligned;" ::: "memory")
#define WG_COMMIT() asm volatile("wgmma.commit_group.sync.aligned;" ::: "memory")
#define WG_WAIT(n) asm volatile("wgmma.wait_group.sync.aligned %0;" ::"n"(n) : "memory")

template <int N>
__device__ __forceinline__ void fence_regs(float* d) {
#pragma unroll
  for (int i = 0; i < N; i++) asm volatile("" : "+f"(d[i])::"memory");
}
__device__ __forceinline__ uint64_t mkdesc(uint32_t addr, uint32_t lbo, uint32_t sbo, uint32_t swz) {
  return (uint64_t)((addr & 0x3FFFF) >> 4) | ((uint64_t)(lbo >> 4) << 16) | ((uint64_t)(sbo >> 4) << 32) |
         ((uint64_t)swz << 62);
}
__device__ __forceinline__ void mbar_init(uint32_t bar, int cnt) {
  asm volatile("mbarrier.init.shared::cta.b64 [%0], %1;" ::"r"(bar), "r"(cnt) : "memory");
}
__device__ __forceinline__ void mbar_expect(uint32_t bar, int bytes) {
  asm volatile("mbarrier.arrive.expect_tx.shared::cta.b64 _, [%0], %1;" ::"r"(bar), "r"(bytes) : "memory");
}
__device__ __forceinline__ void mbar_arrive(uint32_t bar) {
  asm volatile("mbarrier.arrive.shared::cta.b64 _, [%0];" ::"r"(bar) : "memory");
}
__device__ __forceinline__ void mbar_arrive_cl(uint32_t cbar, int cnt) {
  asm volatile("mbarrier.arrive.shared::cluster.b64 _, [%0], %1;" ::"r"(cbar), "r"(cnt) : "memory");
}
__device__ __forceinline__ void mbar_wait(uint32_t bar, int parity) {
  asm volatile("{\n.reg .pred p;\n.reg .u32 c;\nmov.u32 c, 0;\n"
               "W_%=:\nmbarrier.try_wait.parity.shared::cta.b64 p, [%0], %1;\n@p bra D_%=;\n"
               "add.u32 c, c, 1;\nsetp.gt.u32 p, c, 0x400000;\n@p trap;\nbra W_%=;\nD_%=:\n}\n"
               ::"r"(bar), "r"(parity) : "memory");
}
__device__ __forceinline__ void mbar_wait_cl(uint32_t bar, int parity) {
  asm volatile("{\n.reg .pred p;\n.reg .u32 c;\nmov.u32 c, 0;\n"
               "W_%=:\nmbarrier.try_wait.parity.acquire.cluster.shared::cta.b64 p, [%0], %1;\n@p bra D_%=;\n"
               "add.u32 c, c, 1;\nsetp.gt.u32 p, c, 0x400000;\n@p trap;\nbra W_%=;\nD_%=:\n}\n"
               ::"r"(bar), "r"(parity) : "memory");
}
__device__ __forceinline__ void flag_wait(const unsigned* f, unsigned target) {
  asm volatile("{\n.reg .pred p;\n.reg .u32 c, v;\nmov.u32 c, 0;\n"
               "W_%=:\nld.acquire.gpu.global.u32 v, [%0];\nsub.u32 v, v, %1;\nsetp.ge.s32 p, v, 0;\n@p bra D_%=;\n"
               "add.u32 c, c, 1;\nsetp.gt.u32 p, c, 0x400000;\n@p trap;\nnanosleep.u32 20;\nbra W_%=;\nD_%=:\n"
               "fence.proxy.async.global;\n}\n"
               ::"l"(f), "r"(target) : "memory");
}
__device__ __forceinline__ bool mbar_test2(uint32_t bar0, int par0, uint32_t bar1, int par1) {
  uint32_t ok;
  asm volatile("{\n.reg .pred p, q;\nmbarrier.test_wait.parity.shared::cta.b64 p, [%1], %2;\n"
               "mbarrier.test_wait.parity.shared::cta.b64 q, [%3], %4;\nand.pred p, p, q;\n"
               "vote.sync.all.pred p, p, 0xffffffff;\nselp.u32 %0, 1, 0, p;\n}\n"
               : "=r"(ok) : "r"(bar0), "r"(par0), "r"(bar1), "r"(par1) : "memory");
  return ok;
}
__device__ __forceinline__ unsigned flags_poll(const unsigned* f, unsigned target, unsigned need) {
  unsigned m;
  asm volatile("{\n.reg .pred p;\n.reg .u32 c, v;\nmov.u32 c, 0;\n"
               "W_%=:\nld.acquire.gpu.global.u32 v, [%1];\nsub.u32 v, v, %2;\nsetp.ge.s32 p, v, 0;\n"
               "vote.sync.ballot.b32 %0, p, 0xffffffff;\nand.b32 v, %0, %3;\nsetp.eq.u32 p, v, %3;\n@p bra D_%=;\n"
               "add.u32 c, c, 1;\nsetp.gt.u32 p, c, 0x400000;\n@p trap;\nbra W_%=;\nD_%=:\n"
               "bar.warp.sync 0xffffffff;\nfence.proxy.async.global;\n}\n"
               : "=r"(m) : "l"(f), "r"(target), "r"(need) : "memory");
  return m;
}
__device__ __forceinline__ void flags_poll_all(const unsigned* f, unsigned target) {
  asm volatile("{\n.reg .pred p;\n.reg .u32 c, v;\nmov.u32 c, 0;\n"
               "W_%=:\nld.relaxed.gpu.global.u32 v, [%0];\nsub.u32 v, v, %1;\nsetp.ge.s32 p, v, 0;\n"
               "vote.sync.all.pred p, p, 0xffffffff;\n@p bra.uni D_%=;\n"
               "add.u32 c, c, 1;\nsetp.gt.u32 p, c, 0x400000;\n@p trap;\nnanosleep.u32 %2;\nbra.uni W_%=;\nD_%=:\n"
               "fence.proxy.async.global;\n}\n"
               ::"l"(f), "r"(target), "n"(YSLEEP) : "memory");
}
__device__ __forceinline__ void stats_wait(const uint2* s, uint32_t tag, uint2& r0, uint2& r1) {
  asm volatile("{\n.reg .pred p;\n.reg .u32 c, v, w;\nmov.u32 c, 0;\n"
               "W_%=:\nld.relaxed.gpu.global.v2.u32 {%0, %1}, [%4];\nld.relaxed.gpu.global.v2.u32 {%2, %3}, [%4 + 64];\n"
               "xor.b32 v, %0, %5;\nxor.b32 w, %2, %5;\nor.b32 v, v, w;\nsetp.lt.u32 p, v, 0x10000;\n"
               "vote.sync.all.pred p, p, 0xffffffff;\n@p bra.uni D_%=;\n"
               "add.u32 c, c, 1;\nsetp.gt.u32 p, c, 0x400000;\n@p trap;\nbra.uni W_%=;\nD_%=:\n}\n"
               : "=&r"(r0.x), "=&r"(r0.y), "=&r"(r1.x), "=&r"(r1.y) : "l"(s), "r"(tag) : "memory");
}
__device__ __forceinline__ void flag_add(unsigned* f) {
  asm volatile("fence.acq_rel.gpu;\nred.relaxed.gpu.global.add.u32 [%0], 1;" ::"l"(f) : "memory");
}
__device__ __forceinline__ void tma_ld(uint32_t dst, const CUtensorMap* m, int c0, int c1, uint32_t bar) {
  asm volatile("cp.async.bulk.tensor.2d.shared::cluster.global.mbarrier::complete_tx::bytes [%0], [%1, {%3, %4}], [%2];"
               ::"r"(dst), "l"(m), "r"(bar), "r"(c0), "r"(c1) : "memory");
}
__device__ __forceinline__ void tma_ld_mc(uint32_t dst, const CUtensorMap* m, int c0, int c1, uint32_t bar) {
  asm volatile("cp.async.bulk.tensor.2d.shared::cluster.global.mbarrier::complete_tx::bytes.multicast::cluster [%0], [%1, {%3, %4}], [%2], %5;"
               ::"r"(dst), "l"(m), "r"(bar), "r"(c0), "r"(c1), "h"((uint16_t)3) : "memory");
}
template <int TX = 16384>
__device__ __forceinline__ void w_ld_mc(uint32_t bar, uint32_t dst, const CUtensorMap* m, int c0, int c1) {
  asm volatile("{\n.reg .pred p;\nelect.sync _|p, 0xffffffff;\n"
               "@p mbarrier.arrive.expect_tx.shared::cta.b64 _, [%0], %6;\n"
               "@p cp.async.bulk.tensor.2d.shared::cluster.global.mbarrier::complete_tx::bytes.multicast::cluster [%1], [%2, {%3, %4}], [%0], %5;\n}\n"
               ::"r"(bar), "r"(dst), "l"(m), "r"(c0), "r"(c1), "h"((uint16_t)3), "n"(TX) : "memory");
}
__device__ __forceinline__ void w_ld1(uint32_t bar, uint32_t dst, const CUtensorMap* m, int c0, int c1) {
  asm volatile("{\n.reg .pred p;\nelect.sync _|p, 0xffffffff;\n"
               "@p cp.async.bulk.tensor.2d.shared::cluster.global.mbarrier::complete_tx::bytes [%1], [%2, {%3, %4}], [%0];\n}\n"
               ::"r"(bar), "r"(dst), "l"(m), "r"(c0), "r"(c1) : "memory");
}
template <int TX = 16384>
__device__ __forceinline__ void w_ld2(uint32_t bar, uint32_t dst, const CUtensorMap* m, int c0, int c0b, int c1) {
  asm volatile("{\n.reg .pred p;\n.reg .u32 d;\nelect.sync _|p, 0xffffffff;\nadd.u32 d, %1, 8192;\n"
               "@p mbarrier.arrive.expect_tx.shared::cta.b64 _, [%0], %6;\n"
               "@p cp.async.bulk.tensor.2d.shared::cluster.global.mbarrier::complete_tx::bytes [%1], [%2, {%3, %5}], [%0];\n"
               "@p cp.async.bulk.tensor.2d.shared::cluster.global.mbarrier::complete_tx::bytes [d], [%2, {%4, %5}], [%0];\n}\n"
               ::"r"(bar), "r"(dst), "l"(m), "r"(c0), "r"(c0b), "r"(c1), "n"(TX) : "memory");
}
__device__ __forceinline__ void w_arrive(uint32_t bar) {
  asm volatile("{\n.reg .pred p;\nelect.sync _|p, 0xffffffff;\n@p mbarrier.arrive.shared::cta.b64 _, [%0];\n}\n" ::"r"(bar) : "memory");
}
__device__ __forceinline__ void tma_st(const CUtensorMap* m, int c0, int c1, uint32_t src) {
  asm volatile("cp.async.bulk.tensor.2d.global.shared::cta.bulk_group [%0, {%2, %3}], [%1];"
               ::"l"(m), "r"(src), "r"(c0), "r"(c1) : "memory");
}
__device__ __forceinline__ void bulk_ld(uint32_t dst, const void* src, int bytes, uint32_t bar) {
  asm volatile("cp.async.bulk.shared::cluster.global.mbarrier::complete_tx::bytes [%0], [%1], %2, [%3];"
               ::"r"(dst), "l"(src), "r"(bytes), "r"(bar) : "memory");
}
__device__ __forceinline__ void pf_l2(const void* src) { asm volatile("prefetch.global.L2 [%0];" ::"l"(src) : "memory"); }
__device__ __forceinline__ void pf_map(const CUtensorMap* m) {
  asm volatile("prefetch.tensormap [%0];" ::"l"(m) : "memory");
}
__device__ __forceinline__ void ldsm4(uint32_t* r, uint32_t a) {
  asm volatile("ldmatrix.sync.aligned.m8n8.x4.shared.b16 {%0,%1,%2,%3}, [%4];"
               : "=r"(r[0]), "=r"(r[1]), "=r"(r[2]), "=r"(r[3]) : "r"(a) : "memory");
}
__device__ __forceinline__ void ldsm4t(uint32_t* r, uint32_t a) {
  asm volatile("ldmatrix.sync.aligned.m8n8.x4.trans.shared.b16 {%0,%1,%2,%3}, [%4];"
               : "=r"(r[0]), "=r"(r[1]), "=r"(r[2]), "=r"(r[3]) : "r"(a) : "memory");
}
__device__ __forceinline__ void stsm4(uint32_t a, uint32_t r0, uint32_t r1, uint32_t r2, uint32_t r3) {
  asm volatile("stmatrix.sync.aligned.m8n8.x4.shared.b16 [%0], {%1,%2,%3,%4};"
               ::"r"(a), "r"(r0), "r"(r1), "r"(r2), "r"(r3) : "memory");
}
__device__ __forceinline__ uint32_t lds32(uint32_t a) {
  uint32_t v;
  asm volatile("ld.shared.b32 %0, [%1];" : "=r"(v) : "r"(a) : "memory");
  return v;
}
__device__ __forceinline__ uint2 lds64(uint32_t a) {
  uint2 v;
  asm volatile("ld.shared.v2.b32 {%0,%1}, [%2];" : "=r"(v.x), "=r"(v.y) : "r"(a) : "memory");
  return v;
}
__device__ __forceinline__ uint4 lds128(uint32_t a) {
  uint4 v;
  asm volatile("ld.shared.v4.b32 {%0,%1,%2,%3}, [%4];" : "=r"(v.x), "=r"(v.y), "=r"(v.z), "=r"(v.w) : "r"(a) : "memory");
  return v;
}
__device__ __forceinline__ void sts32u(uint32_t a, uint32_t v) {
  asm volatile("st.shared.b32 [%0], %1;" ::"r"(a), "r"(v) : "memory");
}
__device__ __forceinline__ void sts128(uint32_t a, uint32_t x, uint32_t y, uint32_t z, uint32_t w) {
  asm volatile("st.shared.v4.b32 [%0], {%1,%2,%3,%4};" ::"r"(a), "r"(x), "r"(y), "r"(z), "r"(w) : "memory");
}
__device__ __forceinline__ void stg128(void* p, uint32_t x, uint32_t y, uint32_t z, uint32_t w) {
  asm volatile("st.global.v4.b32 [%0], {%1,%2,%3,%4};" ::"l"(p), "r"(x), "r"(y), "r"(z), "r"(w) : "memory");
}
__device__ __forceinline__ void bar_sync(int id, int n) { asm volatile("bar.sync %0, %1;" ::"r"(id), "r"(n) : "memory"); }
__device__ __forceinline__ void bar_arrive(int id, int n) { asm volatile("bar.arrive %0, %1;" ::"r"(id), "r"(n) : "memory"); }
__device__ __forceinline__ uint32_t pack_bf16(float lo, float hi) {
  uint32_t r;
  asm("cvt.rn.bf16x2.f32 %0, %1, %2;" : "=r"(r) : "f"(hi), "f"(lo));
  return r;
}
__device__ __forceinline__ float bf_lo(uint32_t v) { return __uint_as_float(v << 16); }
__device__ __forceinline__ float bf_hi(uint32_t v) { return __uint_as_float(v & 0xffff0000u); }
__device__ __forceinline__ float bf_round(float x) { return bf_lo(pack_bf16(x, 0.f)); }
__device__ __forceinline__ uint32_t bmul2(uint32_t a, uint32_t b) {
  uint32_t r;
  asm("mul.rn.bf16x2 %0, %1, %2;" : "=r"(r) : "r"(a), "r"(b));
  return r;
}
__device__ __forceinline__ uint32_t badd2(uint32_t a, uint32_t b) {
  uint32_t r;
  asm("add.rn.bf16x2 %0, %1, %2;" : "=r"(r) : "r"(a), "r"(b));
  return r;
}
__device__ __forceinline__ uint32_t bfma2(uint32_t a, uint32_t b, uint32_t c) {
  uint32_t r;
  asm("fma.rn.bf16x2 %0, %1, %2, %3;" : "=r"(r) : "r"(a), "r"(b), "r"(c));
  return r;
}
__device__ __forceinline__ uint32_t bsub2(uint32_t a, uint32_t b) {
  uint32_t r;
  asm("sub.rn.bf16x2 %0, %1, %2;" : "=r"(r) : "r"(a), "r"(b));
  return r;
}
__device__ __forceinline__ float sqrt_fast(float x) {
  float r;
  asm("sqrt.approx.f32 %0, %1;" : "=f"(r) : "f"(x));
  return r;
}
__device__ __forceinline__ float rcp_fast(float x) {
  float r;
  asm("rcp.approx.f32 %0, %1;" : "=f"(r) : "f"(x));
  return r;
}
__device__ __forceinline__ void hmma(float* c, uint32_t a0, uint32_t a1, uint32_t a2, uint32_t a3, uint32_t b0, uint32_t b1) {
  asm volatile("mma.sync.aligned.m16n8k16.row.col.f32.bf16.bf16.f32 {%0,%1,%2,%3}, {%4,%5,%6,%7}, {%8,%9}, {%0,%1,%2,%3};"
               : "+f"(c[0]), "+f"(c[1]), "+f"(c[2]), "+f"(c[3]) : "r"(a0), "r"(a1), "r"(a2), "r"(a3), "r"(b0), "r"(b1));
}

__device__ __forceinline__ int g1_block(int f, int r) { return 7 * (f >> 1) + (r == 0 ? 3 : ((f & 1) ? 3 + r : r - 1)); }
__device__ __forceinline__ void geglu_store(const float* d, float ri0, float ri1, uint32_t stg_lane, int rsw) {
  float ca[2] = {0.7978845608028654f * ri0, 0.7978845608028654f * ri1};
  const float cb[2] = {0.044715f * ca[0] * ri0 * ri0, 0.044715f * ca[1] * ri1 * ri1};
#pragma unroll
  for (int j = 0; j < 8; j += 2) {
    uint32_t hp[4];
#pragma unroll
    for (int i = 0; i < 4; i++) {
      const int o = 4 * (j + (i >> 1)) + 2 * (i & 1);
      float r[2], t;
#pragma unroll
      for (int e = 0; e < 2; e++) {
        const float x = d[o + e], pr = x * d[32 + o + e];
        asm("tanh.approx.f32 %0, %1;" : "=f"(t) : "f"(x * fmaf(x * x, cb[i & 1], ca[i & 1])));
        r[e] = fmaf(pr, t, pr);
      }
      hp[i] = pack_bf16(r[0], r[1]);
    }
    stsm4(stg_lane + ((j ^ rsw) << 4), hp[0], hp[1], hp[2], hp[3]);
  }
}

struct ConvEpi {
  uint32_t wr_base, wr_edge, rd_base, y_wr;
  bool qge, up;
  int barid;
  float carry[2];
  uint32_t pcarry;
  uint32_t pv[8];
  uint2 p0, p1, p2, p3;
  __device__ __forceinline__ void combine(const float* d) {
#pragma unroll
    for (int j = 0; j < 8; j++)
      pv[j] = pack_bf16(d[4 * j] + (j == 7 ? carry[0] : d[4 * ((j + 1) & 7) + 2]),
                        d[4 * j + 1] + (j == 7 ? carry[1] : d[4 * ((j + 1) & 7) + 3]));
    const uint32_t e = qge ? pv[0] : pcarry;
    pcarry = pv[0];
    pv[0] = e;
    asm volatile("add.f32 %0, %1, 0f00000000;" : "=f"(carry[0]) : "f"(d[2]));
    asm volatile("add.f32 %0, %1, 0f00000000;" : "=f"(carry[1]) : "f"(d[3]));
  }
  __device__ __forceinline__ void sync() { bar_sync(barid, 128); }
  __device__ __forceinline__ void store(int chunk) {
#pragma unroll
    for (int j = 0; j < 8; j++) sts32u((j ? wr_base + j * 128 : wr_edge) + (chunk & 1) * 4096, pv[j]);
  }
  __device__ __forceinline__ void load(int chunk) {
    const uint32_t r = rd_base + (chunk & 1) * 4096;
    p0 = lds64(r); p1 = lds64(r + 1024); p2 = lds64(r + 2048); p3 = lds64(r + 3072);
  }
  __device__ __forceinline__ void finish(int chunk) {
    const float a0 = (bf_lo(p0.x) + bf_lo(p1.x)) + (bf_lo(p2.x) + bf_lo(p3.x));
    const float a1 = (bf_lo(p0.y) + bf_lo(p1.y)) + (bf_lo(p2.y) + bf_lo(p3.y));
    const float b0 = (bf_hi(p0.x) + bf_hi(p1.x)) + (bf_hi(p2.x) + bf_hi(p3.x));
    const float b1 = (bf_hi(p0.y) + bf_hi(p1.y)) + (bf_hi(p2.y) + bf_hi(p3.y));
    const uint32_t ya = pack_bf16(a0, a1), yb = pack_bf16(b0, b1);
    sts32u(y_wr - 1024 * chunk, up ? yb : ya);
    sts32u((y_wr ^ 16) - 1024 * chunk, up ? ya : yb);
  }
};

struct XChunk {
  uint4 v;
  uint32_t pv;
  __device__ __forceinline__ void fetch(const __nv_bfloat16* ssm, const __nv_bfloat16* dvec, int ch, int chunk) {
    const uint4* src = reinterpret_cast<const uint4*>(ssm + ch * S_) + chunk;
    v = __ldg(src);
    pv = chunk ? __ldg(reinterpret_cast<const uint32_t*>(src) - 1) : __ldg(reinterpret_cast<const unsigned short*>(dvec) + ch);
  }
  __device__ __forceinline__ void put(uint32_t dst, bool first) {
    if (first) v.x = badd2(v.x, pv);
    sts128(dst + XA_OFF, v.x, v.y, v.z, v.w);
    sts128(dst, __byte_perm(pv, v.x, 0x5432), __byte_perm(v.x, v.y, 0x5432), __byte_perm(v.y, v.z, 0x5432),
           __byte_perm(v.z, v.w, 0x5432));
  }
};

__global__ void __cluster_dims__(2, 1, 1) __launch_bounds__(512, 1) fused_kernel(const __grid_constant__ Params p) {
  extern __shared__ __align__(1024) uint8_t smem_raw[];
  if (threadIdx.x < 128) asm volatile("prefetch.global.L2 [%0];" ::"l"(p.qg + blockIdx.x * 8192 + threadIdx.x * 64) : "memory");
  const uint32_t sb = (uint32_t)__cvta_generic_to_shared(smem_raw);
  const uint32_t bar = sb + OFF_BAR;
  const int tid = threadIdx.x, warp = __shfl_sync(~0u, tid >> 5, 0), lane = tid & 31;
  const int b = blockIdx.x, rank = b & 1;
  const int cl = b >> 1;
  const int d7 = ((cl - 36) * 37) >> 8;
  const int idx = min(cl, cl < 36 ? (cl + 28) >> 3 & 3 | (cl < 4 ? 3 : 0) : d7);
  const int grp = cl < 36 ? (cl < 4 ? 0 : 1 + ((cl + 4) & 7)) : cl - 27 - 7 * d7;
  const int m1 = (grp & 14) + rank, f = 2 * idx + (grp & 1);
  const int row2 = grp * 128 + rank * 64, n2 = idx;

  if (lane == 0 && warp >= 4) {
    if (warp == 8 || warp == 10) {
      mbar_init(bar + 8 * (B_FULL + warp - 8), 1);
      mbar_init(bar + 8 * (B_FULL + warp - 7), 1);
      if (warp == 8) TS1(100);
#pragma unroll 1
      for (int s = warp - 8; s < warp - 6; s++) {
        mbar_expect(bar + 8 * (B_FULL + s), SLOT);
        tma_ld(sb + s * SLOT, &p.q, s * 128, m1 * 128 + (f & 1) * 64, bar + 8 * (B_FULL + s));
        tma_ld(sb + s * SLOT + 8192, &p.q, s * 128 + 64, m1 * 128 + (f & 1) * 64, bar + 8 * (B_FULL + s));
        if (warp == 8) TS1(101 + s);
      }
    } else {
      if (warp < 8) {
#pragma unroll
        for (int i = 0; i < 8; i++) mbar_init(bar + 8 * (min(4 + (warp - 4) * 8, B_EMPTY - 8) + i), 1);
      } else if (warp == 9) {
#pragma unroll
        for (int i = 0; i < 11; i++) mbar_init(bar + 8 * (B_EMPTY + i), 16);
      } else if (warp == 11) {
#pragma unroll
        for (int i = B_E2; i < B_SFULL; i++) mbar_init(bar + 8 * i, 8);
      } else {
#pragma unroll
        for (int i = 0; i < 7; i++) mbar_init(bar + 8 * (min(B_SFULL + (warp - 12) * 7, NBAR - 7) + i), 4);
      }
    }
    asm volatile("fence.mbarrier_init.release.cluster;\nfence.acq_rel.cta;" ::: "memory");
  } else if (warp < 2) {
    asm volatile("prefetch.global.L2 [%0];" ::"l"((rank ? p.gwu : p.gwg) + ((grp >> 1) * 64 + tid) * F_ + g1_block(f, 0) * 64) : "memory");
  }
  __syncwarp();
  if (tid == 256) TS1(104);
  if (tid == 128) TS1(105);
  if (tid == 0) TS1(106);
  asm volatile("barrier.cluster.arrive.relaxed.aligned;" ::: "memory");

  if (warp >= 12) {
    asm volatile("setmaxnreg.dec.sync.aligned.u32 40;");
    asm volatile("barrier.cluster.wait.aligned;" ::: "memory");
    {
      const int t0 = 16 * b, tok = (lane & 1) ? 0 : 8;
      const bool halo = (lane & 1) && b;
      int cp = (warp & 3) * 16 + (lane >> 1);
      uint4 sw;
      uint32_t h0 = 0, h1 = 0, h2 = 0;
      auto fetch = [&](int c) {
        sw = __ldg(reinterpret_cast<const uint4*>(p.shift) + c);
        if (halo) {
          const uint32_t* hp = reinterpret_cast<const uint32_t*>(p.k + (t0 - 3) * D_) + c;
          h0 = __ldg(hp); h1 = __ldg(hp + 256); h2 = __ldg(hp + 512);
        }
      };
      mbar_wait(bar + 8 * B_KV, 0);
      TS(119);
      fetch(cp);
#pragma unroll 1
      for (; cp < NPS * 64; cp += 64) {
        asm volatile("mov.b32 %0, %0;" : "+r"(cp));
        const uint32_t kb = sb + OFF_X + cp * 4, ko = kb + tok * 1032;
        uint32_t kr[11], vr[8];
#pragma unroll
        for (int i = 3; i < 11; i++) kr[i] = lds32(ko + (i - 3) * 1024);
#pragma unroll
        for (int i = 0; i < 8; i++) vr[i] = lds32(ko + (OFF_Z - OFF_X) + i * 1024);
        kr[0] = h0; kr[1] = h1; kr[2] = h2;
        if (!(lane & 1)) {
#pragma unroll
          for (int i = 0; i < 3; i++) kr[i] = lds32(kb + (5 + i) * 1024);
        }
        const uint32_t w0 = __byte_perm(sw.x, sw.z, 0x5410), w1 = __byte_perm(sw.x, sw.z, 0x7632);
        const uint32_t w2 = __byte_perm(sw.y, sw.w, 0x5410), w3 = __byte_perm(sw.y, sw.w, 0x7632);
        if (cp < 192) fetch(cp + 64);
#pragma unroll
        for (int i = 0; i < 8; i++)
          vr[i] = bmul2(bfma2(kr[i + 3], w0, bfma2(kr[i + 2], w1, bfma2(kr[i + 1], w2, bmul2(kr[i], w3)))), vr[i]);
        uint4* o = reinterpret_cast<uint4*>(p.ur + (2 * cp) * S_ + (2040 - t0 - tok));
        stg128(o, __byte_perm(vr[7], vr[6], 0x5410), __byte_perm(vr[5], vr[4], 0x5410),
               __byte_perm(vr[3], vr[2], 0x5410), __byte_perm(vr[1], vr[0], 0x5410));
        stg128(o + 256, __byte_perm(vr[7], vr[6], 0x7632), __byte_perm(vr[5], vr[4], 0x7632),
               __byte_perm(vr[3], vr[2], 0x7632), __byte_perm(vr[1], vr[0], 0x7632));
      }
      TS(120);
      bar_sync(5, 128);
      if (tid == 384) {
        mbar_arrive(bar + 8 * B_PREP);
        flag_add(p.flags + FL_KV);
        TS1(84);
      }
      __syncwarp();
    }
    {
      XChunk x[4];
#pragma unroll
      for (int i = 0; i < 4; i++) x[i].fetch(p.ssm, p.dvec, 4 * b + (i >> 1), (i & 1) * 128 + (tid & 127));
#pragma unroll
      for (int i = 0; i < 4; i++) x[i].put(sb + OFF_X + (i >> 1) * XSTRIDE + ((i & 1) * 128 + (tid & 127)) * 16, !(i & 1) && tid == 384);
      __syncwarp();
      if (lane == 0) mbar_arrive(bar + 8 * B_XFULL);
      TS(121);
    }
    mbar_wait(bar + 8 * (B_G1END + 1), 0);
    asm volatile("setmaxnreg.inc.sync.aligned.u32 96;");
    const int w = warp & 3, g = lane >> 2, wtid = tid & 127;
    uint32_t ebar;
    asm("mapa.shared::cluster.u32 %0, %1, %2;" : "=r"(ebar) : "r"(bar + 8 * B_E2), "r"((lane & 1) ^ rank));
#define G2REL(u) do { if (lane < 2) mbar_arrive_cl(ebar + 8 * (u), 1); } while (0)
    const uint32_t da0 = (uint32_t)mkdesc(sb, 16, 1024, 1), db0 = (uint32_t)mkdesc(sb, 8192, 1024, 1);
    const uint64_t hi = (uint64_t)0x40000040u << 32;
    const float ri0 = __uint_as_float(__ldcg(p.stats + row2 + 16 * w + g).y);
    const float ri1 = __uint_as_float(__ldcg(p.stats + row2 + 16 * w + g + 8).y);
    float acc[64];
    bool ready = false, held = false;
    unsigned long long tok = G2_TOK;
    TS(10);
#pragma unroll 1
    for (int lap = 0; lap < 4; lap++) {
#pragma unroll
      for (int u = 0; u < 7; u++) {
        constexpr int NU = 7;
        const int un = (u + 1) % NU, up = (u + NU - 1) % NU;
        const int k = 7 * lap + u;
        const bool paced = k >= G2_PRE && k < G2_PRE + G2_NP, pacedn = k + 1 >= G2_PRE && k + 1 < G2_PRE + G2_NP;
        if (!ready) {
          WG_WAIT(0);
          if (held) G2REL(up);
          held = false;
          if (paced) mbar_wait(bar + 8 * (B_TOK + ((uint32_t)tok & 15)), 0);
          mbar_wait(bar + 8 * (B_G2F + u), lap & 1);
        }
        if (paced) tok >>= 4;
        const uint64_t ca = hi | (da0 + ((uint32_t)(G2_HSUB >> (8 * u)) & 31) * 512);
        const uint64_t cb = hi | (db0 + ((G2_WSLOT >> (4 * u)) & 15) * (SLOT >> 4));
        WG_FENCE();
        wg_ss128_t(acc, ca, cb, k != 0);
        wg_ss128_t(acc, ca + 2, cb + 128, 1);
        WG_COMMIT();
        const int phn = (lap + (u == NU - 1)) & 1;
        ready = mbar_test2(bar + 8 * (B_G2F + un), phn, bar + 8 * (pacedn ? B_TOK + ((uint32_t)tok & 15) : B_G2F + un), pacedn ? 0 : phn);
        WG_WAIT(1);
        if (held) G2REL(up);
        WG_FENCE();
        wg_ss128_t(acc, ca + 4, cb + 256, 1);
        wg_ss128_t(acc, ca + 6, cb + 384, 1);
        WG_COMMIT();
        held = lap < 3;
        if (k == G2_PRE + G2_NP - 1) TS(42);
      }
    }
    TS(19);
    const float f0 = 0.5f * ri0 * ri0, f1 = 0.5f * ri1 * ri1;
    WG_WAIT(0);
    fence_regs<64>(acc);
    TS(21);
#pragma unroll
    for (int j = 0; j < 8; j++) {
      const float* c = acc + 8 * j;
      sts128(sb + OFF_BT + j * 2048 + wtid * 16, pack_bf16(c[0] * f0, c[1] * f0), pack_bf16(c[2] * f1, c[3] * f1),
             pack_bf16(c[4] * f0, c[5] * f0), pack_bf16(c[6] * f1, c[7] * f1));
    }
    bar_arrive(3, 384);
    TS(22);
  } else if (warp >= 8) {
    asm volatile("setmaxnreg.dec.sync.aligned.u32 24;");
    asm volatile("barrier.cluster.wait.aligned;" ::: "memory");
    const unsigned* const epp = p.flags + FL_EP + b * FLS;
    const CUtensorMap* const wm = rank ? &p.wu : &p.wg;
    if (warp == 8) {
#pragma unroll 1
      for (int s = 0; s < 4; s++) {
        mbar_wait(bar + 8 * (B_EMPTY + s), 0);
        w_arrive(bar + 8 * (B_FULL + s));
        w_ld2(bar + 8 * (B_QB + s), sb + s * SLOT, &p.q, s * 128, s * 128 + 64, m1 * 128 + ((f & 1) ^ 1) * 64);
      }
      if (lane == 0) {
        TS1(103);
        pf_map(&p.h); pf_map(&p.wd); pf_map(&p.y);
      }
#pragma unroll 1
      for (int e = 0; e < 7; e++) {
        const int a = e & 1, r = (e + 1) >> 1;
        mbar_wait(bar + 8 * (B_SFULL + a), (e >> 1) & 1);
        if (lane == 0) {
          tma_st(&p.h, g1_block(f, r) * 64, m1 * 128 + (a ^ (f & 1)) * 64, sb + OFF_STG + a * 8192);
          asm volatile("cp.async.bulk.commit_group;\ncp.async.bulk.wait_group 0;\nfence.proxy.async.global;" ::: "memory");
          mbar_arrive(bar + 8 * (B_SEMPTY + a));
          asm volatile("red.relaxed.gpu.global.add.u32 [%0], 1;" ::"l"(p.flags + FL_H + ((m1 * 8 + (r ? f : f & 6)) * 4 + r) * FLS) : "memory");
          TS1(88 + e);
        }
        __syncwarp();
      }
    } else if (warp == 9) {
      if (W0DELAY) __nanosleep(W0DELAY);
#pragma unroll 1
      for (int i = 0; i < 8; i += 2)
        w_ld_mc(bar + 8 * (B_FULL + (i ? 3 + i : 10)), sb + (i ? 3 + i : 10) * SLOT + rank * 8192, wm, g1_block(f, 0) * 64, i * 64);
      if (lane == 0) TS1(115);
      int slot = 0, ph = 1, col = g1_block(f, 1) * 64;
#pragma unroll 1
      for (int i = 0; i < 24; i++) {
        if (i < 4) mbar_wait(bar + 8 * (B_QB + i), 0);
        if (i == 10) mbar_wait(bar + 8 * B_T7, 0);
        mbar_wait(bar + 8 * (B_EMPTY + slot), ph);
        w_ld_mc(bar + 8 * (B_FULL + slot), sb + slot * SLOT + rank * 8192, wm, col, (i & 7) * 64);
        if (i == 4 || i == 10) w_arrive(bar + 8 * (B_W1GO + (i == 10)));
        if ((i & 7) == 7) col += 64;
        if (++slot == NSLOT) slot = 0;
        ph ^= (0x411 >> slot) & 1;
      }
    }
    if (warp < 10) {
      const unsigned ep1 = __ldcg(epp) + 1;
      const unsigned* lflag = p.flags + FL_H + ((grp * 8 + (lane < 4 ? 2 * lane : (lane - 4) & 7)) * 4 + (((lane + 4) >> 3) & 3)) * FLS;
      unsigned ready = 0;
#pragma unroll 1
      for (int k = warp == 8 ? G2_JOIN : 0; k < 28; k += (k + 1 < G2_JOIN) ? 1 : 2) {
        const int lap = (k * 37) >> 8, u = k - 7 * lap;
        const int kc = (k < 4 ? 7 * k + 3 : 7 * (((k - 4) >> 1) & 3) + ((k - 4) >> 3) + 4 * (k & 1)) * 64;
        const int ws = (G2_WSLOT >> (4 * u)) & 15, hs = (int)(G2_HSUB >> (8 * u)) & 31;
        const uint32_t fb = bar + 8 * (B_G2F + u);
        if (!((ready >> k) & 1)) ready = flags_poll(lflag, 2 * ep1, 1u << k);
        if (k < 7) {
          mbar_wait(bar + 8 * (B_EMPTY + ws), (G1_LASTPH >> ws) & 1);
          mbar_wait(bar + 8 * (B_EMPTY + (hs >> 1)), (G1_LASTPH >> (hs >> 1)) & 1);
        } else {
          mbar_wait(bar + 8 * (B_E2 + u), ~lap & 1);
        }
        w_ld_mc<24576>(fb, sb + ws * SLOT + rank * 8192, &p.wd, n2 * 128 + rank * 64, kc);
        w_ld1(fb, sb + hs * 8192, &p.h, kc, row2);
        if (lane == 0 && !(k & 1)) TS1(64 + (k >> 1));
      }
    } else {
      const int a = warp - 10;
      const int t0 = 16 * b;
      if (a == 0) {
        if (W0DELAY) __nanosleep(W0DELAY);
#pragma unroll 1
        for (int i = 1; i < 7; i += 2)
          w_ld_mc(bar + 8 * (B_FULL + 3 + i), sb + (3 + i) * SLOT + rank * 8192, wm, g1_block(f, 0) * 64, i * 64);
        mbar_wait(bar + 8 * (B_EMPTY + 10), 0);
        w_ld_mc(bar + 8 * (B_FULL + 10), sb + 10 * SLOT + rank * 8192, wm, g1_block(f, 0) * 64, 7 * 64);
        w_arrive(bar + 8 * B_T7);
      } else {
        __nanosleep(W1PF);
        const __nv_bfloat16* wp = (rank ? p.gwu : p.gwg) + ((grp >> 1) * 64 + lane) * F_ + g1_block(f, 1) * 64;
        pf_l2(wp);
        pf_l2(wp + 32 * F_);
      }
      mbar_wait(bar + 8 * (B_QB + 3), 0);
      if (tid == 320) mbar_expect(bar + 8 * B_KV, 32768);
      if (a) pf_l2(p.shift + lane * 64);
#pragma unroll 1
      for (int i = 0; i < 8; i++) {
        if (i >= 4) pf_l2((a ? p.ssm + b * 8192 : p.gwd + min(b * 7168, F_ * D_ - 8192)) + ((i - 4) * 32 + lane) * 64);
        else if (lane == 0) bulk_ld(sb + (a ? OFF_Z : OFF_X) + i * 4096 + (i >> 1) * 64, (a ? p.v : p.k) + (t0 + 4 * i) * D_, 4096, bar + 8 * B_KV);
        if (i == 3 && tid == 320) TS1(118);
        __nanosleep(PFSLEEP);
      }
      const unsigned ep1 = __ldcg(epp) + 1;
      mbar_wait(bar + 8 * B_PREP, 0);
      if (lane < 2) sts128(sb + OFF_Z + (2 * lane + a) * ZSTRIDE + 4096, 0, 0, 0, 0);
      asm volatile("fence.proxy.async.shared::cta;" ::: "memory");
      if (lane == 0) {
        flag_wait(p.flags + FL_KV, 128 * ep1);
        mbar_expect(bar + 8 * (B_ZFULL + a), 8192);
        bulk_ld(sb + OFF_Z + a * ZSTRIDE, p.ur + (4 * b + a) * S_, 4096, bar + 8 * (B_ZFULL + a));
        bulk_ld(sb + OFF_Z + (2 + a) * ZSTRIDE, p.ur + (4 * b + 2 + a) * S_, 4096, bar + 8 * (B_ZFULL + a));
        TS1(86 + a);
      }
      __syncwarp();
#pragma unroll 1
      for (int c = 0; c < 2; c++) {
        mbar_wait(bar + 8 * (B_YDONE + 2 * a + c), 0);
        if (lane == 0) {
          asm volatile("cp.async.bulk.global.shared::cta.bulk_group [%0], [%1], 4096;\ncp.async.bulk.commit_group;\n"
                       "cp.async.bulk.wait_group 0;\nfence.proxy.async.global;"
                       ::"l"(p.yt + (4 * b + 2 * c + a) * S_), "r"(sb + OFF_YB + a * 4096) : "memory");
          if (c) asm volatile("st.relaxed.gpu.global.u32 [%0], %1;" ::"l"(p.flags + FL_Y + YSTR * b + a), "r"(ep1) : "memory");
          else mbar_arrive(bar + 8 * (B_YFREE + a));
          TS1(96 + a * 2 + c);
          TG(132 + a);
        }
        __syncwarp();
      }
      mbar_wait(bar + 8 * (B_YDONE + 3 - 2 * a), 0);
      if (lane == 0) TG(136 + a);
      flags_poll_all(p.flags + FL_Y + YSTR * (32 * n2 + 16 * a + (lane >> 1)) + (lane & 1), ep1);
      if (lane == 0) {
        mbar_expect(bar + 8 * (B_YT + a), 8192);
        tma_ld(sb + OFF_YT + a * 8192, &p.y, row2, n2 * 128 + a * 64, bar + 8 * (B_YT + a));
        TS1(80 + a);
        TG(134 + a);
        if (a == 0) p.flags[FL_EP + b * FLS] = ep1;
      }
    }
  } else {
    asm volatile("setmaxnreg.inc.sync.aligned.u32 224;");
    const int wg = warp >> 2, w = warp & 3, g = lane >> 2, q = lane & 3, wtid = tid & 127;
    uint32_t ebar;
    asm("mapa.shared::cluster.u32 %0, %1, %2;" : "=r"(ebar) : "r"(bar + 8 * B_EMPTY), "r"((lane & 1) ^ rank));
    if (tid == 0) TS1(107);
    asm volatile("barrier.cluster.wait.aligned;" ::: "memory");
    if (tid == 0) TS1(108);
    const int mrow = 16 * w + (lane & 7) + ((lane >> 3) & 1) * 8;
    const int rsw = ((lane >> 4) ^ (lane & 7));
    const uint32_t stg = sb + OFF_STG + wg * 8192;
    {
      uint32_t a[128];
      float ri0 = 0.f, ri1 = 0.f;
      float cs[NSET][4] = {}, c0[NSET][4] = {}, c1[NSET][4] = {};
      const uint32_t tag = (__ldcg(p.flags + FL_EP + b * FLS) + 1) << 16;
      uint2* const stp = p.stats + m1 * 128 + ((f & 1) ^ wg) * 64 + 16 * w + g;
#pragma unroll
      for (int sl = 0; sl < 4; sl++) {
        mbar_wait(bar + 8 * ((wg ? B_QB : B_FULL) + sl), 0);
        TS(109 + 19 * wg + sl);
        const uint32_t base = sb + sl * SLOT + mrow * 128;
#pragma unroll
        for (int kk = 0; kk < 8; kk++) ldsm4(a + (sl * 8 + kk) * 4, base + (kk >> 2) * 8192 + ((((kk & 3) * 2) ^ rsw) << 4));
#pragma unroll
        for (int h = 0; h < 2; h++) {
          if (wg == 0) {
#pragma unroll
            for (int kk = h ? RELAT : 0; kk < (h ? 8 : RELAT); kk++) {
              const uint32_t* r = a + (sl * 8 + kk) * 4;
              hmma(cs[kk % NSET], r[0], r[1], r[2], r[3], 0x3f803f80u, 0x3f803f80u);
              hmma(c0[kk % NSET], r[0], r[1], r[2], r[3], r[0], r[2]);
              hmma(c1[kk % NSET], r[0], r[1], r[2], r[3], r[1], r[3]);
            }
          }
          if (h == 0 && lane < 2)
            asm volatile("{\n.reg .pred p;\nsetp.eq.u32 p, %1, 0;\n@p mbarrier.arrive.shared::cluster.b64 _, [%0], 2;\n"
                         "@!p mbarrier.arrive.shared::cluster.b64 _, [%0], 2;\n}\n" ::"r"(ebar + 8 * sl), "r"(a[sl * 32 + 31]) : "memory");
        }
      }
      TS(0 + 32 * wg);
      uint32_t m0, m1p;
      if (wg == 0) {
#pragma unroll
        for (int i = 1; i < NSET; i++)
#pragma unroll
          for (int j = 0; j < 4; j++) { cs[0][j] += cs[i][j]; c0[0][j] += c0[i][j]; c1[0][j] += c1[i][j]; }
        const float s0 = cs[0][0] * (1.f / D_), s1 = cs[0][2] * (1.f / D_);
        m0 = pack_bf16(s0, s0);
        m1p = pack_bf16(s1, s1);
        const float ss0 = __shfl_sync(~0u, (g & 1) ? c0[0][1] : c0[0][0], 4 * g + (g >> 1));
        const float ss1 = __shfl_sync(~0u, (g & 1) ? c1[0][3] : c1[0][2], 4 * g + (g >> 1));
        const float v0 = fmaxf(fmaf(-s0, s0, ss0 * (1.f / D_)), 0.f), v1 = fmaxf(fmaf(-s1, s1, ss1 * (1.f / D_)), 0.f);
        ri0 = rcp_fast(bf_round(sqrt_fast(bf_round(bf_round(v0) + 1e-5f))));
        ri1 = rcp_fast(bf_round(sqrt_fast(bf_round(bf_round(v1) + 1e-5f))));
        if (f < 2 && q == 0) {
          __stcg(stp, make_uint2((m0 & 0xffffu) | tag, __float_as_uint(ri0)));
          __stcg(stp + 8, make_uint2((m1p & 0xffffu) | tag, __float_as_uint(ri1)));
        }
      } else {
        uint2 t0, t1;
        stats_wait(stp, tag, t0, t1);
        m0 = __byte_perm(t0.x, 0, 0x1010);
        m1p = __byte_perm(t1.x, 0, 0x1010);
        ri0 = __uint_as_float(t0.y);
        ri1 = __uint_as_float(t1.y);
      }
#pragma unroll
      for (int i = 0; i < 128; i++) a[i] = bsub2(a[i], (i & 1) ? m1p : m0);
      TS(1 + 32 * wg);
      const uint32_t fb0 = bar + 8 * B_FULL, dl0 = (uint32_t)mkdesc(sb, 8192, 1024, 1);
      uint32_t fb = fb0 + 8 * (wg ? 0 : 10), dl = dl0 + (wg ? 0 : 10) * (SLOT >> 4), ph = 0;
#pragma unroll 1
      for (int rd = wg; rd < 4; rd++) {
        float d[64];
        uint32_t prev = 0;
        const int cnt = rd ? 1 : 2;
        if (rd > wg) mbar_wait(bar + 8 * (B_LAG + wg), (rd - 1 - wg) & 1);
        mbar_wait(fb, ph);
#pragma unroll
        for (int kb = 0; kb < 8; kb++) {
          const uint64_t db = ((uint64_t)0x40000040u << 32) | dl;
          const uint32_t cur = fb;
          fb += 8; dl += SLOT >> 4;
          if (fb == fb0 + 8 * NSLOT) { fb = fb0; dl = dl0; }
          if (fb == fb0 || fb == fb0 + 8 * 10 || (fb == fb0 + 8 * 4 && rd)) ph ^= 1;
          if (kb == 0 && rd == 0) { fb = fb0 + 8 * 4; dl = dl0 + 4 * (SLOT >> 4); ph = 0; }
          if (kb == 3 && rd == 1) mbar_wait(bar + 8 * B_W1GO, 0);
          if (kb == 1 && rd == 2) mbar_wait(bar + 8 * (B_W1GO + 1), 0);
          WG_FENCE();
          wg_rs128_t(d, a + (kb * 4 + 0) * 4, db, kb != 0);
          wg_rs128_t(d, a + (kb * 4 + 1) * 4, db + 128, 1);
          if (kb == KLAG && wg == 1 && lane == 0) mbar_arrive(bar + 8 * B_LAG);
          if (kb == KLEAD && wg == 0 && rd > 0 && lane == 0) mbar_arrive(bar + 8 * (B_LAG + 1));
          if (kb < 7) mbar_wait(fb, ph);
          WG_FENCE();
          wg_rs128_t(d, a + (kb * 4 + 2) * 4, db + 256, 1);
          wg_rs128_t(d, a + (kb * 4 + 3) * 4, db + 384, 1);
          WG_COMMIT();
          if (kb > 0) {
            WG_WAIT(1);
            if (lane < 2) mbar_arrive_cl(ebar + (prev - fb0), cnt);
          }
          prev = cur;
        }
        WG_WAIT(0);
        fence_regs<64>(d);
        if (lane < 2) mbar_arrive_cl(ebar + (prev - fb0), cnt);
        TS(2 + 2 * rd + 32 * wg);
        if (rd > wg) mbar_wait(bar + 8 * (B_SEMPTY + wg), (rd - wg - 1) & 1);
        geglu_store(d, ri0, ri1, stg + mrow * 128, rsw);
        asm volatile("fence.proxy.async.shared::cta;" ::: "memory");
        __syncwarp();
        if (lane == 0) mbar_arrive(bar + 8 * (B_SFULL + wg));
        TS(3 + 2 * rd + 32 * wg);
        if (rd == 0) mbar_wait(bar + 8 * (B_QB + 3), 0);
      }
    }
    asm volatile("setmaxnreg.dec.sync.aligned.u32 168;");
    if (lane == 0) mbar_arrive(bar + 8 * (B_G1END + wg));
    {
      const uint32_t xb = sb + OFF_X + wg * XSTRIDE;
      const int o0 = 16 * w + g + 2 * q - 7;
      const uint32_t xa = xb + ((g & 1) ? XA_OFF + 2 * o0 : 2 * (o0 + 1));
      const uint32_t amask = (o0 >= 0) ? 0xffffffffu : (o0 == -1 ? 0xffff0000u : 0u);
      ConvEpi E;
      {
        const uint32_t wr0 = stg + w * 1024 + (((q - w) & 3) * 8 + g) * 4;
        E.qge = q >= w;
        E.wr_base = wr0 - (E.qge ? 0 : 128);
        E.wr_edge = wr0 + (E.qge ? 0 : 7 * 128);
        E.rd_base = stg + wtid * 8;
        E.up = lane >= 16;
        E.y_wr = sb + OFF_YB + wg * 4096 + 16 * (255 - 2 * (wtid >> 2) - (lane >> 4)) + 4 * (wtid & 3);
        E.barid = 1 + wg;
      }
      uint32_t a[64];
      auto a_load = [&](int i) {
        a[4 * i + 0] = lds32(xa + 256 * i);
        a[4 * i + 1] = lds32(xa + 256 * i + 128);
        a[4 * i + 2] = lds32(xa + 256 * i + 16);
        a[4 * i + 3] = lds32(xa + 256 * i + 144);
      };
      XChunk xn0, xn1;
      xn0.fetch(p.ssm, p.dvec, 4 * b + 2 + wg, wtid);
      xn1.fetch(p.ssm, p.dvec, 4 * b + 2 + wg, 128 + wtid);
      mbar_wait(bar + 8 * B_XFULL, 0);
#pragma unroll
      for (int i = 0; i < 4; i++) a_load(i);
      mbar_wait(bar + 8 * (B_ZFULL + wg), 0);
#pragma unroll 1
      for (int c = 0; c < 2; c++) {
        a[0] &= amask;
        const uint64_t dz = mkdesc(sb + OFF_Z + (2 * c + wg) * ZSTRIDE, 16, 128, 0);
        float d0[32], d1[32];
        E.carry[0] = E.carry[1] = 0.f;
        E.pcarry = 0;
#define CV(d, i, off) wg_rs64_n(d, a + 4 * (i), dz + (off) + 16 * (i), (i) != 0)
#define CVT(d, i, off) conv_tail(d, a + 4 * (i), dz + (off) + 16 * (i))
        auto token = [&](int ch) {
          const int e = 4 * c + 3 - ch;
          if (lane == 0) mbar_arrive(bar + 8 * (B_TOK + (wg ? (e < 2 ? e : 2 * e - 1) : (e < 6 ? 2 * e + 2 : e + 8))));
        };
#define TOKEN(ch) do { token(ch); WG_FENCE(); } while (0)
        WG_FENCE();
        CV(d0, 0, 192); CVT(d0, 1, 192);
        WG_COMMIT();
        CV(d1, 0, 128); a_load(4); CV(d1, 1, 128); a_load(5);
        WG_COMMIT();
        WG_WAIT(1);
        fence_regs<32>(d0);
        if (c == 0) mbar_wait(bar + 8 * (B_SEMPTY + wg), (3 - wg) & 1);
        mbar_wait(bar + 8 * (c ? B_YFREE + wg : B_EMPTY + OFF_YB / SLOT), c ? 0 : (G1_LASTPH >> (OFF_YB / SLOT)) & 1);
        TS(11 + 4 * c + 32 * wg);
        WG_FENCE();
        E.combine(d0); CV(d1, 2, 128); E.store(3); a_load(6); a_load(7); CV(d1, 3, 128); E.sync(); E.load(3);
        WG_FENCE();
        CV(d1, 4, 128); CVT(d1, 5, 128);
        WG_COMMIT();
        CV(d0, 0, 64); a_load(8); CV(d0, 1, 64); E.finish(3); CV(d0, 2, 64);
        WG_COMMIT();
        WG_WAIT(1);
        fence_regs<32>(d1);
        TOKEN(3);
        CV(d0, 3, 64); E.combine(d1); a_load(9); CV(d0, 4, 64); E.store(2); a_load(10); CV(d0, 5, 64); a_load(11); E.sync();
        CV(d0, 6, 64); E.load(2); CV(d0, 7, 64);
        WG_FENCE();
        CV(d0, 8, 64); CVT(d0, 9, 64);
        WG_COMMIT();
        TS(12 + 4 * c + 32 * wg);
        CV(d1, 0, 0); CV(d1, 1, 0); E.finish(2); CV(d1, 2, 0);
        WG_COMMIT();
        WG_WAIT(1);
        fence_regs<32>(d0);
        TOKEN(2);
        CV(d1, 3, 0); E.combine(d0); CV(d1, 4, 0); E.store(1); a_load(12); CV(d1, 5, 0); a_load(13); CV(d1, 6, 0); E.sync();
        CV(d1, 7, 0); E.load(1); CV(d1, 8, 0);
        if (c == 0) { xn0.put(xb + wtid * 16, wtid == 0); if (w == 0) xn1.put(xb + (128 + wtid) * 16, false); }
        WG_FENCE();
        a_load(14); CV(d1, 9, 0); a_load(15); CV(d1, 10, 0); E.finish(1); CV(d1, 11, 0);
        TOKEN(1);
        CV(d1, 12, 0); CVT(d1, 13, 0);
        WG_COMMIT();
        WG_WAIT(0);
        fence_regs<32>(d1);
        TS(13 + 4 * c + 32 * wg);
        E.combine(d1); E.store(0); E.sync(); E.load(0); a_load(0); a_load(1); a_load(2); a_load(3); E.finish(0);
        if (c == 0 && w != 0) xn1.put(xb + (128 + wtid) * 16, false);
        asm volatile("fence.proxy.async.shared::cta;" ::: "memory");
        __syncwarp();
        if (lane == 0) mbar_arrive(bar + 8 * (B_YDONE + 2 * wg + c));
        TOKEN(0);
        TS(14 + 4 * c + 32 * wg);
      }
    }
    {
      int t2;
      asm volatile("mov.u32 %0, %%tid.x;" : "=r"(t2));
      const int lane = t2 & 31, w = (t2 >> 5) & 3, g = lane >> 2, q = lane & 3, wtid = t2 & 127;
      uint32_t xv[16];
      const uint32_t* xp = reinterpret_cast<const uint32_t*>(p.qg + (row2 + 16 * w + g) * D_ + n2 * 128 + wg * 64) + q;
#pragma unroll
      for (int j = 0; j < 16; j++) xv[j] = __ldg(xp + (j >> 1) * 4 + (j & 1) * 8 * (D_ / 2));
      const uint2 st0 = __ldcg(p.stats + row2 + 16 * w + g), st1 = __ldcg(p.stats + row2 + 16 * w + g + 8);
      const uint32_t mu0 = __byte_perm(st0.x, 0, 0x1010), mu1 = __byte_perm(st1.x, 0, 0x1010);
      uint32_t xn[16];
#pragma unroll
      for (int j = 0; j < 16; j++) {
        const uint32_t dd = bsub2(xv[j], (j & 1) ? mu1 : mu0);
        const float ri = __uint_as_float((j & 1) ? st1.y : st0.y);
        xn[j] = pack_bf16(bf_lo(dd) * ri, bf_hi(dd) * ri);
      }
      const uint32_t yl = sb + OFF_YT + wg * 8192 + ((lane & 7) + (lane >> 4) * 8) * 128 +
                          (((2 * w + ((lane >> 3) & 1)) ^ (lane & 7)) << 4);
      const int mrow = 16 * w + (lane & 7) + ((lane >> 3) & 1) * 8, rsw = (lane >> 4) ^ (lane & 7);
      uint4* op = reinterpret_cast<uint4*>(p.outp + (row2 + 16 * w + (lane >> 3)) * D_ + n2 * 128 + wg * 64) + (lane & 7);
      mbar_wait(bar + 8 * (B_YT + wg), 0);
      TS(20 + 32 * wg);
#pragma unroll
      for (int j = 0; j < 8; j += 2) {
        uint32_t yv[4];
        ldsm4t(yv, yl + j * 1024);
#pragma unroll
        for (int i = 0; i < 4; i++) xv[2 * j + i] = badd2(xv[2 * j + i], bmul2(xn[2 * j + i], yv[i]));
      }
      bar_sync(3, 384);
      TS(53);
#pragma unroll
      for (int j = 0; j < 8; j += 2) {
        const uint4 f = lds128(sb + OFF_BT + (4 * wg + (j >> 1)) * 2048 + wtid * 16);
        stsm4(stg + mrow * 128 + ((j ^ rsw) << 4), badd2(xv[2 * j], f.x), badd2(xv[2 * j + 1], f.y),
              badd2(xv[2 * j + 2], f.z), badd2(xv[2 * j + 3], f.w));
      }
      __syncwarp();
#pragma unroll
      for (int i = 0; i < 4; i++) {
        const int r = 4 * i + (lane >> 3);
        op[i * 4 * (D_ / 8)] = lds128(stg + (16 * w + r) * 128 + (((lane & 7) ^ (r & 7)) << 4));
      }
      TS(54);
    }
  }
}

typedef CUresult (*EncodeFn)(CUtensorMap*, CUtensorMapDataType, cuuint32_t, void*, const cuuint64_t*, const cuuint64_t*,
                             const cuuint32_t*, const cuuint32_t*, CUtensorMapInterleave, CUtensorMapSwizzle,
                             CUtensorMapL2promotion, CUtensorMapFloatOOBfill);

void make_map(EncodeFn enc, CUtensorMap* m, const void* base, int cols, int rows, int bc, int br, CUtensorMapSwizzle sw,
              CUtensorMapL2promotion pr = CU_TENSOR_MAP_L2_PROMOTION_L2_128B) {
  cuuint64_t gd[2] = {(cuuint64_t)cols, (cuuint64_t)rows}, gs[1] = {(cuuint64_t)cols * 2};
  cuuint32_t bd[2] = {(cuuint32_t)bc, (cuuint32_t)br}, es[2] = {1, 1};
  enc(m, CU_TENSOR_MAP_DATA_TYPE_BFLOAT16, 2, const_cast<void*>(base), gd, gs, bd, es, CU_TENSOR_MAP_INTERLEAVE_NONE, sw,
      pr, CU_TENSOR_MAP_FLOAT_OOB_FILL_NONE);
}

}

extern "C" void kernel_launch(void* const* d_in, const int* in_sizes, int n_in, void* d_out, int out_size) {
  (void)in_sizes; (void)n_in; (void)out_size;
  void* fn = nullptr;
  cudaDriverEntryPointQueryResult st;
  cudaGetDriverEntryPoint("cuTensorMapEncodeTiled", &fn, cudaEnableDefault, &st);
  EncodeFn enc = (EncodeFn)fn;
  Params p;
  void *h, *ur, *yt, *stats, *flags;
  cudaGetSymbolAddress(&h, g_h);
  cudaGetSymbolAddress(&ur, g_ur);
  cudaGetSymbolAddress(&yt, g_yt);
  cudaGetSymbolAddress(&stats, g_stats);
  cudaGetSymbolAddress(&flags, g_flags);
  const auto SW128 = CU_TENSOR_MAP_SWIZZLE_128B;
  make_map(enc, &p.q, d_in[0], D_, S_, 64, 64, SW128, CU_TENSOR_MAP_L2_PROMOTION_L2_256B);
  make_map(enc, &p.wg, d_in[7], F_, D_, 64, 64, SW128);
  make_map(enc, &p.wu, d_in[8], F_, D_, 64, 64, SW128);
  make_map(enc, &p.h, h, F_, S_, 64, 64, SW128);
  make_map(enc, &p.wd, d_in[9], D_, F_, 64, 64, SW128);
  make_map(enc, &p.y, yt, S_, D_, 64, 64, SW128);
  p.qg = (const __nv_bfloat16*)d_in[0];
  p.k = (const __nv_bfloat16*)d_in[1];
  p.v = (const __nv_bfloat16*)d_in[2];
  p.shift = (const __nv_bfloat16*)d_in[3];
  p.ssm = (const __nv_bfloat16*)d_in[4];
  p.dvec = (const __nv_bfloat16*)d_in[5];
  p.gwg = (const __nv_bfloat16*)d_in[7];
  p.gwu = (const __nv_bfloat16*)d_in[8];
  p.gwd = (const __nv_bfloat16*)d_in[9];
  p.outp = (__nv_bfloat16*)d_out;
  p.ur = (__nv_bfloat16*)ur;
  p.yt = (__nv_bfloat16*)yt;
  p.stats = (uint2*)stats;
  p.flags = (unsigned*)flags;
  cudaFuncSetAttribute(fused_kernel, cudaFuncAttributeMaxDynamicSharedMemorySize, SMEM_BYTES);
  fused_kernel<<<128, 512, SMEM_BYTES, cudaStreamPerThread>>>(p);
}
```
